```python
import torch

def _softmax(x, axis=-1):
    return torch.softmax(x, dim=axis)
def _gelu(x):
    return torch.nn.functional.gelu(x, approximate="tanh")
def _silu(x):
    return torch.nn.functional.silu(x)
def _sigmoid(x):
    return torch.sigmoid(x)
def _layernorm(x, axis=-1, eps=1e-5):
    m = x.mean(dim=axis, keepdim=True)
    v = x.var(dim=axis, keepdim=True, unbiased=False)
    return (x - m) / torch.sqrt(v + eps)
def _scatter_add(tgt, idx, src, axis=0):
    return tgt.clone().index_add_(axis, idx, src)
def _segment_sum(src, seg, n):
    out = torch.zeros((n,) + src.shape[1:], dtype=src.dtype)
    return out.index_add_(0, seg, src)
def _pad(x, pw):
    flat = tuple(v for pair in reversed(pw) for v in pair)
    return torch.nn.functional.pad(x, flat)

kernel_name = 'concat_heads__mha_block_cached__mha_block_cached__near_ridge'

def setup_inputs():

    _w = (lambda a: (lambda t: t.to(torch.bfloat16) if t.is_floating_point() else t)(torch.as_tensor(a)))
    def _A_setup():
        B, Sq, D = 8, 96, 448
        H, Sk, Dh = 16, 512, 256
        return {
            "x": _w((lambda *s: torch.randn(*s, dtype=torch.bfloat16) * 0.8)(B, Sq, D)),
            "k_cache": _w((lambda *s: torch.randn(*s, dtype=torch.bfloat16) * 0.8)(B, H, Sk, Dh)),
            "v_cache": _w((lambda *s: torch.randn(*s, dtype=torch.bfloat16) * 0.05)(B, H, Sk, Dh)),
            "wq": _w((lambda *s: torch.randn(*s, dtype=torch.bfloat16) * 0.8)(D, H * Dh) * (D ** -0.5)),
            "wo": _w((lambda *s: torch.randn(*s, dtype=torch.bfloat16) * 0.05)(H * Dh, D) * ((H * Dh) ** -0.5)),
        }
    _A_in = _A_setup()

    def _B_setup():
        B, Sq, D = 8, 96, 448
        H, Sk, Dh = 16, 512, 256
        return {
            "x": _w((lambda *s: torch.randn(*s, dtype=torch.bfloat16) * 0.8)(B, Sq, D)),
            "k_cache": _w((lambda *s: torch.randn(*s, dtype=torch.bfloat16) * 0.8)(B, H, Sk, Dh)),
            "v_cache": _w((lambda *s: torch.randn(*s, dtype=torch.bfloat16) * 0.05)(B, H, Sk, Dh)),
            "wq": _w((lambda *s: torch.randn(*s, dtype=torch.bfloat16) * 0.8)(D, H * Dh) * (D ** -0.5)),
            "wo": _w((lambda *s: torch.randn(*s, dtype=torch.bfloat16) * 0.05)(H * Dh, D) * ((H * Dh) ** -0.5)),
        }
    _B_in = _B_setup()

    return {
        "A_x": _A_in["x"],
        "A_k_cache": _A_in["k_cache"],
        "A_v_cache": _A_in["v_cache"],
        "A_wq": _A_in["wq"],
        "A_wo": _A_in["wo"],
        "B_x": _B_in["x"],
        "B_k_cache": _B_in["k_cache"],
        "B_v_cache": _B_in["v_cache"],
        "B_wq": _B_in["wq"],
        "B_wo": _B_in["wo"],
    }

def reference(A_x, A_k_cache, A_v_cache, A_wq, A_wo, B_x, B_k_cache, B_v_cache, B_wq, B_wo):
    def _A_ref(x, k_cache, v_cache, wq, wo):
        B, Sq, D = x.shape
        H, Dh = 16, 256
        q = (lambda x, *d: x.permute(*d))((x @ wq).reshape(B, Sq, H, Dh), 0, 2, 1, 3)
        scores = torch.einsum("bhqd,bhkd->bhqk", q, k_cache) * (Dh ** -0.5)
        p = _softmax(scores, axis=-1)
        o = torch.einsum("bhqk,bhkd->bhqd", p, v_cache)
        return (lambda x, *d: x.permute(*d))(o, 0, 2, 1, 3).reshape(B, Sq, H * Dh) @ wo

    def _B_ref(x, k_cache, v_cache, wq, wo):
        B, Sq, D = x.shape
        H, Dh = 16, 256
        q = (lambda x, *d: x.permute(*d))((x @ wq).reshape(B, Sq, H, Dh), 0, 2, 1, 3)
        scores = torch.einsum("bhqd,bhkd->bhqk", q, k_cache) * (Dh ** -0.5)
        p = _softmax(scores, axis=-1)
        o = torch.einsum("bhqk,bhkd->bhqd", p, v_cache)
        return (lambda x, *d: x.permute(*d))(o, 0, 2, 1, 3).reshape(B, Sq, H * Dh) @ wo

    a = _A_ref(A_x, A_k_cache, A_v_cache, A_wq, A_wo)
    b = _B_ref(B_x, B_k_cache, B_v_cache, B_wq, B_wo)
    return torch.concatenate([a, b], axis=-1)
```

```cpp
#include <cuda_runtime.h>
#include <cuda_bf16.h>
#include <cuda.h>
#include <stdint.h>

namespace {

constexpr int NSTAGE   = 10;
constexpr int BOX      = 8192;
constexpr int CHUNK    = 12288;
constexpr int SLOT     = 49152;
constexpr int OFF_S0   = 0;
constexpr int OFF_S1   = SLOT;
constexpr int OFF_S2   = 2 * SLOT;
constexpr int OFF_RING = 3 * SLOT;
constexpr int OFF_MISC = OFF_RING + NSTAGE * BOX;
constexpr int OFF_FULL   = OFF_MISC;
constexpr int OFF_EMPTY  = OFF_MISC + 256;
constexpr int OFF_XFULL  = OFF_MISC + 384;
constexpr int OFF_O2FULL = OFF_MISC + 440;
constexpr int OFF_O1FREE = OFF_MISC + 472;
constexpr int OFF_EPBAR  = OFF_MISC + 504;
constexpr int OFF_EPOCH  = OFF_MISC + 512;
constexpr int OFF_PFBAR  = OFF_MISC + 528;
constexpr int OFF_CMAX   = OFF_MISC + 576;
constexpr int OFF_CSUM   = OFF_CMAX + 768;
constexpr int SMEM_BYTES = 232448;

#define PF_K 196608
#define PF_WQ 1
#define V_PROMO CU_TENSOR_MAP_L2_PROMOTION_L2_128B
#define LL_ST "st.global.v4.b32"
#define LL_LD "ld.relaxed.gpu.global.v4.b32"
#define LL_HINT 1
#define PF_G 0
#define PF_G0 65536
#define LL_TMA 0
#define PF_K_LD 1
#define PF_K_SLEEP 200
#define ADAPT 0
#define PF_TM 1
#define EARLY_WG0 true
constexpr int NTHREADS = 384;
constexpr uint32_t SPIN_LIMIT = 1u << 22;

struct __align__(64) Params {
    CUtensorMap m[10];
    __nv_bfloat16* out;
    const unsigned char* ptr[10];
};

__device__ uint4    g_ll[128 * 7 * 8 * 128];
__device__ unsigned g_epoch;
__device__ unsigned g_arrive;

__device__ __forceinline__ uint32_t smem_u32(const void* p) { return (uint32_t)__cvta_generic_to_shared(p); }
__device__ __forceinline__ void mbar_init(uint32_t bar, uint32_t cnt) {
    asm volatile("mbarrier.init.shared::cta.b64 [%0], %1;" :: "r"(bar), "r"(cnt) : "memory");
}
__device__ __forceinline__ void mbar_expect_tx(uint32_t bar, uint32_t bytes) {
    asm volatile("mbarrier.arrive.expect_tx.shared::cta.b64 _, [%0], %1;" :: "r"(bar), "r"(bytes) : "memory");
}
__device__ __forceinline__ void mbar_arrive(uint32_t bar) {
    asm volatile("mbarrier.arrive.shared::cta.b64 _, [%0];" :: "r"(bar) : "memory");
}
__device__ __forceinline__ void mbar_wait(uint32_t bar, uint32_t parity) {
    asm volatile("{\n.reg .pred p;\n.reg .u32 c;\nmov.u32 c, 0;\n"
                 "LW_%=:\nmbarrier.try_wait.parity.shared::cta.b64 p, [%0], %1;\n@p bra LD_%=;\n"
                 "add.u32 c, c, 1;\nsetp.lt.u32 p, c, 4194304;\n@p bra LW_%=;\nLD_%=:\n}"
                 :: "r"(bar), "r"(parity) : "memory");
}
__device__ __forceinline__ bool mbar_test(uint32_t bar, uint32_t parity) {
    uint32_t ok;
    asm volatile("{\n.reg .pred p;\nmbarrier.test_wait.parity.shared::cta.b64 p, [%1], %2;\nselp.u32 %0, 1, 0, p;\n}"
                 : "=r"(ok) : "r"(bar), "r"(parity) : "memory");
    return __all_sync(0xffffffffu, ok != 0);
}
__device__ __forceinline__ void mbar_wait_sleep(uint32_t bar, uint32_t parity) {
    for (uint32_t it = 0; it < (1u << 16); it++) {
        uint32_t ok;
        asm volatile("{\n.reg .pred p;\nmbarrier.test_wait.parity.shared::cta.b64 p, [%1], %2;\nselp.u32 %0, 1, 0, p;\n}"
                     : "=r"(ok) : "r"(bar), "r"(parity) : "memory");
        if (ok) break;
        __nanosleep(256);
    }
}
__device__ __forceinline__ void tma2d(uint32_t dst, const CUtensorMap* m, int c0, int c1, uint32_t bar) {
    asm volatile("cp.async.bulk.tensor.2d.shared::cluster.global.mbarrier::complete_tx::bytes [%0], [%1, {%3, %4}], [%2];"
                 :: "r"(dst), "l"(m), "r"(bar), "r"(c0), "r"(c1) : "memory");
}
__device__ __forceinline__ void fence_async() { asm volatile("fence.proxy.async.shared::cta;" ::: "memory"); }
__device__ __forceinline__ void bar_sync(int id, int n) { asm volatile("bar.sync %0, %1;" :: "r"(id), "r"(n) : "memory"); }
__device__ __forceinline__ void wg_fence()  { asm volatile("wgmma.fence.sync.aligned;" ::: "memory"); }
__device__ __forceinline__ void wg_commit() { asm volatile("wgmma.commit_group.sync.aligned;" ::: "memory"); }
template <int N> __device__ __forceinline__ void wg_wait() { asm volatile("wgmma.wait_group.sync.aligned %0;" :: "n"(N) : "memory"); }

__device__ __forceinline__ uint32_t desc_lo(uint32_t addr) { return ((addr & 0x3FFFF) >> 4) | (1u << 16); }

template <int TA>
__device__ __forceinline__ void wgmma96(float (&d)[48], uint32_t da, uint32_t db, int scale_d) {
    asm volatile("{\n.reg .pred p;\n.reg .b64 da, db;\nsetp.ne.b32 p, %50, 0;\n"
        "mov.b64 da, {%48, 0x40000040};\nmov.b64 db, {%49, 0x40000040};\n"
        "wgmma.mma_async.sync.aligned.m64n96k16.f32.bf16.bf16 "
        "{%0,%1,%2,%3,%4,%5,%6,%7,%8,%9,%10,%11,%12,%13,%14,%15,%16,%17,%18,%19,%20,%21,%22,%23,"
        "%24,%25,%26,%27,%28,%29,%30,%31,%32,%33,%34,%35,%36,%37,%38,%39,%40,%41,%42,%43,%44,%45,%46,%47},"
        " da, db, p, 1, 1, %51, 0;\n}"
        : "+f"(d[0]), "+f"(d[1]), "+f"(d[2]), "+f"(d[3]), "+f"(d[4]), "+f"(d[5]), "+f"(d[6]), "+f"(d[7]),
          "+f"(d[8]), "+f"(d[9]), "+f"(d[10]), "+f"(d[11]), "+f"(d[12]), "+f"(d[13]), "+f"(d[14]), "+f"(d[15]),
          "+f"(d[16]), "+f"(d[17]), "+f"(d[18]), "+f"(d[19]), "+f"(d[20]), "+f"(d[21]), "+f"(d[22]), "+f"(d[23]),
          "+f"(d[24]), "+f"(d[25]), "+f"(d[26]), "+f"(d[27]), "+f"(d[28]), "+f"(d[29]), "+f"(d[30]), "+f"(d[31]),
          "+f"(d[32]), "+f"(d[33]), "+f"(d[34]), "+f"(d[35]), "+f"(d[36]), "+f"(d[37]), "+f"(d[38]), "+f"(d[39]),
          "+f"(d[40]), "+f"(d[41]), "+f"(d[42]), "+f"(d[43]), "+f"(d[44]), "+f"(d[45]), "+f"(d[46]), "+f"(d[47])
        : "r"(da), "r"(db), "r"(scale_d), "n"(TA));
}

__device__ __forceinline__ uint32_t pack_bf16(float lo, float hi) {
    uint32_t r;
    asm("cvt.rn.bf16x2.f32 %0, %1, %2;" : "=r"(r) : "f"(hi), "f"(lo));
    return r;
}
__device__ __forceinline__ void stsm_x4_t(uint32_t addr, uint32_t r0, uint32_t r1, uint32_t r2, uint32_t r3) {
    asm volatile("stmatrix.sync.aligned.m8n8.x4.trans.shared.b16 [%0], {%1,%2,%3,%4};"
                 :: "r"(addr), "r"(r0), "r"(r1), "r"(r2), "r"(r3) : "memory");
}
__device__ __forceinline__ float ex2(float x) { float y; asm("ex2.approx.ftz.f32 %0, %1;" : "=f"(y) : "f"(x)); return y; }
__device__ __forceinline__ float4 lds128(uint32_t addr) {
    float4 v;
    asm volatile("ld.shared.v4.f32 {%0,%1,%2,%3}, [%4];" : "=f"(v.x), "=f"(v.y), "=f"(v.z), "=f"(v.w) : "r"(addr) : "memory");
    return v;
}
__device__ __forceinline__ void ld_ll(uint4& p, const uint4* a) {
    asm volatile(LL_LD " {%0,%1,%2,%3}, [%4];"
                 : "=r"(p.x), "=r"(p.y), "=r"(p.z), "=r"(p.w) : "l"(a) : "memory");
}
__device__ __forceinline__ uint32_t touch_line(const void* a) {
    uint32_t v;
    asm volatile("ld.global.cg.L2::128B.u32 %0, [%1];" : "=r"(v) : "l"(a));
    return v;
}
__device__ __forceinline__ int f2ord(float f) { int i = __float_as_int(f); return i ^ ((i >> 31) & 0x7fffffff); }
__device__ __forceinline__ float ord2f(int i) { return __int_as_float(i ^ ((i >> 31) & 0x7fffffff)); }

#define TS(role, idx) do {} while (0)
#define TSC(role, idx) do {} while (0)

struct Ring {
    uint32_t base;
    uint32_t fullb;
    uint32_t slot, par;
    uint32_t pend;
    bool     leader;
    __device__ __forceinline__ void adv(uint32_t n) {
        slot += n;
        if (slot >= NSTAGE) slot -= NSTAGE;
    }
    template <int TA, bool EARLY = false>
    __device__ __forceinline__ void mma(float (&acc)[48], uint32_t b_addr, bool zero_first, uint32_t n) {
        if (ADAPT && !EARLY) {
            if (!mbar_test(fullb + slot * 8, (par >> slot) & 1)) {
                wg_wait<0>();
                if (pend) mbar_arrive(pend);
                pend = 0;
                mbar_wait(fullb + slot * 8, (par >> slot) & 1);
            }
        } else {
            mbar_wait(fullb + slot * 8, (par >> slot) & 1);
        }
        par ^= 1u << slot;
        const uint32_t da = desc_lo(base + OFF_RING + slot * BOX), db = desc_lo(b_addr);
        wg_fence();
#pragma unroll
        for (int ks = 0; ks < 4; ks++)
            wgmma96<TA>(acc, da + (TA ? ks * 128 : ks * 2), db + ks * 2, (ks > 0 || !zero_first) ? 1 : 0);
        wg_commit();
        if (EARLY) {
            wg_wait<0>();
            if (leader) mbar_arrive(base + OFF_EMPTY + slot * 8);
        } else {
            wg_wait<1>();
            if (pend) mbar_arrive(pend);
            pend = leader ? base + OFF_EMPTY + slot * 8 : 0;
        }
        adv(n);
    }
    __device__ __forceinline__ void drain() {
        wg_wait<0>();
        if (pend) mbar_arrive(pend);
        pend = 0;
    }
};

__device__ __forceinline__ void store_tile(const float (&a)[48], uint32_t addr) {
#pragma unroll
    for (int jj = 0; jj < 6; jj++)
        stsm_x4_t(addr + jj * 2048,
                  pack_bf16(a[8 * jj + 0], a[8 * jj + 1]), pack_bf16(a[8 * jj + 2], a[8 * jj + 3]),
                  pack_bf16(a[8 * jj + 4], a[8 * jj + 5]), pack_bf16(a[8 * jj + 6], a[8 * jj + 7]));
}
__device__ __forceinline__ void store_tile_scaled(const float (&a)[48], uint32_t addr, uint32_t inv_addr) {
#pragma unroll
    for (int jj = 0; jj < 6; jj++) {
        const float4 s = lds128(inv_addr + jj * 16);
        stsm_x4_t(addr + jj * 2048,
                  pack_bf16(a[8 * jj + 0] * s.x, a[8 * jj + 1] * s.y), pack_bf16(a[8 * jj + 2] * s.x, a[8 * jj + 3] * s.y),
                  pack_bf16(a[8 * jj + 4] * s.z, a[8 * jj + 5] * s.w), pack_bf16(a[8 * jj + 6] * s.z, a[8 * jj + 7] * s.w));
    }
}

__device__ __forceinline__ void ll_write_tile(const float (&a)[48], uint32_t stage, uint4* dst, uint32_t tag, int bar_id, int tw) {
#pragma unroll
    for (int pk = 0; pk < 8; pk++) {
        const int r = 12 * (pk & 3) + 2 * (pk >> 2);
        const uint32_t x = pack_bf16(a[r], a[r + 1]);
        const uint32_t z = pack_bf16(a[r + 4], a[r + 5]);
        const uint32_t yw = pack_bf16(a[r + 8], a[r + 9]);
        const uint32_t y = (yw & 0xffffu) | tag, w = (yw >> 16) | tag;
        asm volatile(LL_ST " [%0], {%1,%2,%3,%4};"
                     :: "l"(dst + pk * 128 + tw), "r"(x), "r"(y), "r"(z), "r"(w) : "memory");
    }
}

__device__ __forceinline__ void softmax_max(const float (&acc)[4][48], uint32_t cmax, int lane) {
    const bool b4 = lane & 16, b3 = lane & 8, b2 = lane & 4;
#pragma unroll
    for (int h = 0; h < 2; h++) {
        float m12[12], m6[6];
#pragma unroll
        for (int i = 0; i < 12; i++) {
            const int r = 24 * h + 4 * (i >> 1) + (i & 1);
            float m = fmaxf(acc[0][r], acc[0][r + 2]);
#pragma unroll
            for (int t = 1; t < 4; t++) m = fmaxf(m, fmaxf(acc[t][r], acc[t][r + 2]));
            m12[i] = m;
        }
#pragma unroll
        for (int i = 0; i < 6; i++) {
            const float snd = b4 ? m12[i] : m12[i + 6], keep = b4 ? m12[i + 6] : m12[i];
            m6[i] = fmaxf(keep, __shfl_xor_sync(0xffffffffu, snd, 16));
        }
#pragma unroll
        for (int i = 0; i < 3; i++) {
            const float snd = b3 ? m6[i] : m6[i + 3], keep = b3 ? m6[i + 3] : m6[i];
            float m = fmaxf(keep, __shfl_xor_sync(0xffffffffu, snd, 8));
            m = fmaxf(m, __shfl_xor_sync(0xffffffffu, m, 4));
            if (!b2)
                asm volatile("red.shared.max.s32 [%0], %1;"
                             :: "r"(cmax + (12 * h + (b4 ? 6 : 0) + (b3 ? 3 : 0) + i) * 4), "r"(f2ord(m)) : "memory");
        }
    }
}
__device__ __forceinline__ void softmax_exp(float (&acc)[4][48], uint32_t p_addr, uint32_t cmax, int lane) {
    const float C = 0.0625f * 1.4426950408889634f;
    const uint32_t csum = cmax + (OFF_CSUM - OFF_CMAX);
    const bool b4 = lane & 16, b3 = lane & 8, b2 = lane & 4;
    float v[24];
#pragma unroll
    for (int jj = 0; jj < 6; jj++) {
        const float4 mo = lds128(cmax + jj * 16);
        const float m0 = ord2f(__float_as_int(mo.x)) * C, m1 = ord2f(__float_as_int(mo.y)) * C;
        const float m2 = ord2f(__float_as_int(mo.z)) * C, m3 = ord2f(__float_as_int(mo.w)) * C;
        float s0 = 0.f, s1 = 0.f, s2 = 0.f, s3 = 0.f;
#pragma unroll
        for (int t = 0; t < 4; t++) {
            float* a = &acc[t][8 * jj];
            const float p0 = ex2(fmaf(a[0], C, -m0)), p1 = ex2(fmaf(a[1], C, -m1));
            const float p2 = ex2(fmaf(a[2], C, -m0)), p3 = ex2(fmaf(a[3], C, -m1));
            const float p4 = ex2(fmaf(a[4], C, -m2)), p5 = ex2(fmaf(a[5], C, -m3));
            const float p6 = ex2(fmaf(a[6], C, -m2)), p7 = ex2(fmaf(a[7], C, -m3));
            s0 += p0 + p2; s1 += p1 + p3; s2 += p4 + p6; s3 += p5 + p7;
            if (t < 2) {
                stsm_x4_t(p_addr + 2 * t * CHUNK + jj * 2048,
                          pack_bf16(p0, p1), pack_bf16(p2, p3), pack_bf16(p4, p5), pack_bf16(p6, p7));
            } else {
                a[0] = p0; a[1] = p1; a[2] = p2; a[3] = p3; a[4] = p4; a[5] = p5; a[6] = p6; a[7] = p7;
            }
        }
        v[4 * jj + 0] = s0; v[4 * jj + 1] = s1; v[4 * jj + 2] = s2; v[4 * jj + 3] = s3;
    }
    float t12[12], t6[6];
#pragma unroll
    for (int i = 0; i < 12; i++) {
        const float snd = b4 ? v[i] : v[i + 12], keep = b4 ? v[i + 12] : v[i];
        t12[i] = keep + __shfl_xor_sync(0xffffffffu, snd, 16);
    }
#pragma unroll
    for (int i = 0; i < 6; i++) {
        const float snd = b3 ? t12[i] : t12[i + 6], keep = b3 ? t12[i + 6] : t12[i];
        t6[i] = keep + __shfl_xor_sync(0xffffffffu, snd, 8);
    }
#pragma unroll
    for (int i = 0; i < 3; i++) {
        const float snd = b2 ? t6[i] : t6[i + 3], keep = b2 ? t6[i + 3] : t6[i];
        const float o = keep + __shfl_xor_sync(0xffffffffu, snd, 4);
        asm volatile("red.shared.add.u32 [%0], %1;"
                     :: "r"(csum + ((b4 ? 12 : 0) + (b3 ? 6 : 0) + (b2 ? 3 : 0) + i) * 4), "r"(__float2uint_rn(o * 4194304.f)) : "memory");
    }
}
__device__ __forceinline__ void invert_sum(uint32_t addr) {
    uint32_t sum;
    asm volatile("ld.shared.u32 %0, [%1];" : "=r"(sum) : "r"(addr) : "memory");
    const float inv = __fdividef(4194304.f, (float)sum);
    asm volatile("st.shared.f32 [%0], %1;" :: "r"(addr), "f"(inv) : "memory");
}

__global__ void __launch_bounds__(NTHREADS, 1)
mha_fused_kernel(const __grid_constant__ Params prm) {
    extern __shared__ __align__(1024) unsigned char smem_raw[];
    const uint32_t sb = (smem_u32(smem_raw) + 1023u) & ~1023u;
    const int tid = threadIdx.x, wg = tid >> 7, lane = tid & 31, warp = (tid >> 5) & 3;
    const int bid = blockIdx.x;
    const int blk = bid >> 6, b = ((bid >> 4) & 3) * 2 + (bid & 1), hp = (bid >> 1) & 7;

    const CUtensorMap* mbase = &prm.m[blk * 5];
    if (tid == 0) {
#pragma unroll
        for (int i = 0; i < NSTAGE; i++) {
            mbar_init(sb + OFF_FULL + i * 8, 1); mbar_init(sb + OFF_FULL + 128 + i * 8, 1); mbar_init(sb + OFF_EMPTY + i * 8, 4);
        }
#pragma unroll
        for (int i = 0; i < 7; i++) mbar_init(sb + OFF_XFULL + i * 8, 1);
#pragma unroll
        for (int i = 0; i < 4; i++) { mbar_init(sb + OFF_O2FULL + i * 8, 128); mbar_init(sb + OFF_O1FREE + i * 8, 4); }
        mbar_init(sb + OFF_EPBAR, 1);
        mbar_init(sb + OFF_PFBAR, 1);
        asm volatile("fence.mbarrier_init.release.cluster;" ::: "memory");
    } else if (tid >= 128 && tid < 320) {
        asm volatile("st.shared.u32 [%0], %1;" :: "r"(sb + OFF_CMAX + (tid - 128) * 4), "r"(0x80000000u) : "memory");
        asm volatile("st.shared.u32 [%0], %1;" :: "r"(sb + OFF_CSUM + (tid - 128) * 4), "r"(0u) : "memory");
    }
    __syncthreads();

    if (wg == 2) {
        asm volatile("setmaxnreg.dec.sync.aligned.u32 24;");
        if (tid < 320) {
            const int h0 = 2 * hp, kv0 = (b * 16 + h0) * 512;
            TS(2, 0);
            if (warp == 1 && lane < 7) {
                mbar_expect_tx(sb + OFF_XFULL + lane * 8, CHUNK);
                tma2d(sb + OFF_S0 + lane * CHUNK, mbase, lane * 64, b * 96, sb + OFF_XFULL + lane * 8);
            }
#pragma unroll 1
            for (int n = 2 * lane + warp; n < 256; n += 64) {
                int owner = n & 1, mi, c0, c1;
                if (n < 56) {
                    mi = 3; c0 = (h0 + owner) * 256 + ((n >> 1) & 3) * 64; c1 = (n >> 3) * 64;
                } else if (n < 120) {
                    const int m = n - 56;
                    mi = 1; c0 = ((m >> 1) & 3) * 64; c1 = kv0 + ((m >> 3) * 2 + owner) * 64;
                } else if (n < 152) {
                    const int m = n - 120;
                    mi = 2; c0 = (owner * 2 + ((m >> 1) & 1)) * 64; c1 = kv0 + (m >> 2) * 64;
                } else {
                    const int j = n - 152;
                    const int hs = j < 77 ? j / 11 : 7, r = j - hs * 11;
                    int kind, i;
                    if (hs < 7) { i = r / 3; kind = r - 3 * i; }
                    else if (r < 4) { i = r; kind = 0; }
                    else { i = (r - 4) >> 1; kind = 1 + ((r - 4) & 1); }
                    owner = kind != 1;
                    if (kind == 0) {
                        mi = 2; c0 = (hs >> 1) * 64; c1 = kv0 + 512 + ((hs & 1) * 4 + i) * 64;
                    } else {
                        mi = 4; c0 = ((kind - 1) * 4 + i) * 64; c1 = h0 * 256 + ((0x76534210u >> (4 * hs)) & 7) * 64;
                    }
                }
                const int use = n / NSTAGE, slot = n - use * NSTAGE;
                const uint32_t eb = sb + OFF_EMPTY + slot * 8, fb = sb + OFF_FULL + owner * 128 + slot * 8;
                const uint32_t dst = sb + OFF_RING + slot * BOX;
                const CUtensorMap* mp = mbase + mi;
                const int cnt = n < 192 ? 32 : 24;
#pragma unroll 1
                for (int i = 0; i < cnt; i++) {
                    if (lane == i) {
                        mbar_wait(eb, (use ^ 1) & 1);
                        mbar_expect_tx(fb, BOX);
                        tma2d(dst, mp, c0, c1, fb);
                    }
                    __syncwarp();
                    if ((i & 3) == 3) TS(2, 1 + (n >> 6) * 8 + (i >> 2));
                }
            }
        } else {
            if (tid == 320) {
                unsigned epoch;
                asm volatile("ld.relaxed.gpu.global.u32 %0, [%1];" : "=r"(epoch) : "l"(&g_epoch) : "memory");
                asm volatile("st.shared.u32 [%0], %1;" :: "r"(sb + OFF_EPOCH), "r"((epoch % 65535u + 1u) << 16) : "memory");
                mbar_arrive(sb + OFF_EPBAR);
                const unsigned old = atomicAdd(&g_arrive, 1u + (epoch & 0u));
                if (old == gridDim.x - 1) { g_arrive = 0; g_epoch = epoch + 1; }
            }
            const int pt = tid - 320;
            uint32_t sink = 0;
            if (PF_TM && tid >= 352 && tid < 355)
                asm volatile("prefetch.tensormap [%0];" :: "l"(mbase + (tid == 354 ? 4 : tid - 351)) : "memory");
            if (PF_WQ) {
                const unsigned char* qp = prm.ptr[blk * 5 + 3] + (size_t)(b * 8 + (pt >> 3)) * 8192 + hp * 1024 + (pt & 7) * 128;
#pragma unroll
                for (int kc = 0; kc < 7; kc++) sink += touch_line(qp + kc * 524288);
            }
            const unsigned char* kp = prm.ptr[blk * 5 + 1] + (size_t)(b * 16 + 2 * hp) * 262144 + pt * 128;
#pragma unroll 1
            for (int i = 0; i < PF_K / 32768; i++) {
                const uint32_t a0 = touch_line(kp + i * 32768), a1 = touch_line(kp + i * 32768 + 8192);
                const uint32_t a2 = touch_line(kp + i * 32768 + 16384), a3 = touch_line(kp + i * 32768 + 24576);
                sink += a0 + a1 + a2 + a3;
            }
            if (PF_G > 0) {
                mbar_wait_sleep(sb + OFF_PFBAR, 0);
                kp += 262144 + PF_G0;
#pragma unroll 1
                for (int i = 0; i < PF_G / 8192; i++) asm volatile("prefetch.global.L2 [%0];" :: "l"(kp + i * 8192));
            }
            if (sink == 0x9e3779b9u) asm volatile("st.shared.u32 [%0], %1;" :: "r"(sb + OFF_EPOCH + 4), "r"(sink) : "memory");
        }
    } else {
        asm volatile("setmaxnreg.inc.sync.aligned.u32 240;");
        float acc[4][48];
        Ring rg;
        rg.base = sb; rg.fullb = sb + OFF_FULL + wg * 128; rg.slot = wg; rg.par = 0; rg.pend = 0; rg.leader = (lane == 0);
        const uint32_t st_base = sb + (uint32_t)((((lane >> 4) & 1) * 8 + (lane & 7)) * 128 +
                                                 (((2 * warp + ((lane >> 3) & 1)) ^ (lane & 7)) << 4));
        TS(wg, 0); TSC(wg, 0);
#pragma unroll 1
        for (int kc = 0; kc < 7; kc++) {
            mbar_wait(sb + OFF_XFULL + kc * 8, 0);
            if (kc == 0) TS(wg, 30);
#pragma unroll
            for (int mt = 0; mt < 4; mt++) rg.mma<1>(acc[mt], sb + OFF_S0 + kc * CHUNK, kc == 0, 2);
            if (kc == 0) TS(wg, 29);
        }
        rg.drain();
        TS(wg, 1);
        if (wg == 1) bar_sync(1, 256);
#pragma unroll
        for (int mt = 0; mt < 4; mt++) store_tile(acc[mt], st_base + (wg == 0 ? OFF_S2 : OFF_S0) + mt * CHUNK);
        fence_async();
        if (wg == 0) bar_sync(1, 256);
        TS(wg, 2);
        const uint32_t o_base = sb + OFF_S2;
        const uint32_t cinv = sb + OFF_CSUM + (lane & 3) * 96;
#pragma unroll 1
        for (int item = 0; item < 2; item++) {
            const uint32_t q_base = sb + (item == 0 ? OFF_S2 : OFF_S0);
#pragma unroll
            for (int t = 0; t < 4; t++) {
#pragma unroll 1
                for (int kc = 0; kc < 4; kc++) rg.mma<0>(acc[t], q_base + kc * CHUNK, kc == 0, 2);
            }
            rg.drain();
            TS(wg, 3 + item * 2);
            if (PF_G > 0 && tid == 0 && item == 0) mbar_arrive(sb + OFF_PFBAR);
            const uint32_t cmax = sb + OFF_CMAX + item * 384 + (lane & 3) * 96;
            const uint32_t p_addr = st_base + (item == 0 ? OFF_S1 : OFF_S0) + wg * CHUNK;
            softmax_max(acc, cmax, lane);
            bar_sync(1, 256);
            softmax_exp(acc, p_addr, cmax, lane);
            if (item == 1) {
                TS(wg, 6);
                if (tid < 96) invert_sum(sb + OFF_CSUM + tid * 4);
#pragma unroll 1
                for (int kc = 0; kc < 8; kc++) {
                    rg.mma<1>(acc[0], sb + OFF_S1 + kc * CHUNK, kc == 0, 2);
                    rg.mma<1>(acc[1], sb + OFF_S1 + kc * CHUNK, kc == 0, 2);
                }
                rg.drain();
                TS(wg, 7);
                bar_sync(1, 256);
                store_tile_scaled(acc[0], st_base + OFF_S2 + 2 * wg * CHUNK, cinv);
                store_tile_scaled(acc[1], st_base + OFF_S2 + (2 * wg + 1) * CHUNK, cinv);
            }
            store_tile(acc[2], p_addr + 4 * CHUNK);
            store_tile(acc[3], p_addr + 6 * CHUNK);
            fence_async();
            if (item == 0) TS(wg, 4);
        }
        bar_sync(1, 256);
        TS(wg, 8);
        mbar_wait(sb + OFF_EPBAR, 0);
        uint32_t tag;
        asm volatile("ld.shared.u32 %0, [%1];" : "=r"(tag) : "r"(sb + OFF_EPOCH) : "memory");
        uint4* const dst = &g_ll[((size_t)((blk * 8 + b) * 8 + hp) * 7 + wg * 4) * 1024];
        const int tw = tid & 127;
        const uint32_t stg = sb + OFF_S0 + (wg == 0 ? 49152 : 0);
        if (wg == 0) {
            rg.adv(1);
#pragma unroll 1
            for (int hs = 0; hs < 7; hs++) {
                const int part = (0x68 >> hs) & 1, ch = (0x2130210 >> (4 * hs)) & 3;
                const uint32_t oc = o_base + ch * CHUNK;
                if (part) mbar_wait(sb + OFF_O2FULL + ch * 8, 0);
                rg.mma<1, EARLY_WG0>(acc[0], oc, hs == 0, 3);
                rg.mma<1, EARLY_WG0>(acc[1], oc, hs == 0, 3);
                rg.mma<1, EARLY_WG0>(acc[2], oc, hs == 0, 3);
                rg.mma<1, EARLY_WG0>(acc[3], oc, hs == 0, 2);
                rg.drain();
                if (!part && lane == 0) mbar_arrive(sb + OFF_O1FREE + ch * 8);
            }
            rg.adv(3);
            mbar_wait(sb + OFF_O2FULL + 24, 0);
            TS(wg, 16);
            rg.mma<1>(acc[0], o_base + 3 * CHUNK, false, 2);
            rg.mma<1>(acc[1], o_base + 3 * CHUNK, false, 2);
            ll_write_tile(acc[0], stg, dst, tag, 2 + wg, tw);
            rg.mma<1>(acc[2], o_base + 3 * CHUNK, false, 2);
            ll_write_tile(acc[1], stg + 16384, dst + 1024, tag, 2 + wg, tw);
            rg.mma<1>(acc[3], o_base + 3 * CHUNK, false, 2);
            ll_write_tile(acc[2], stg + 32768, dst + 2048, tag, 2 + wg, tw);
            wg_wait<0>();
            TS(wg, 17);
            ll_write_tile(acc[3], stg + 49152, dst + 3072, tag, 2 + wg, tw);
        } else {
            rg.adv(NSTAGE - 1);
            if (tid < 128 + 96) invert_sum(sb + OFF_CSUM + 384 + (tid - 128) * 4);
            bar_sync(3, 128);
#pragma unroll 1
            for (int hs = 0; hs < 8; hs++) {
                const int part = (0x68 >> hs) & 1, ch = (0x2130210 >> (4 * hs)) & 3;
                const uint32_t oc = o_base + ch * CHUNK;
                const uint32_t pc = sb + OFF_S0 + (hs & 1) * 4 * CHUNK;
                const uint32_t a = hs < 7 ? 2 : 1;
#pragma unroll
                for (int i = 0; i < 4; i++) {
                    rg.mma<1>(acc[3], pc + i * CHUNK, (hs & 1) == 0 && i == 0, a);
                    if (hs < 7 && i < 3) {
                        if (i == 0 && part) mbar_wait(sb + OFF_O2FULL + ch * 8, 0);
                        rg.mma<1>(acc[i], oc, hs == 0, 1);
                    }
                }
                if (hs & 1) {
                    const int c = hs >> 1;
                    rg.drain();
                    mbar_wait(sb + OFF_O1FREE + c * 8, 0);
                    store_tile_scaled(acc[3], st_base + OFF_S2 + c * CHUNK, cinv + 384);
                    fence_async();
                    mbar_arrive(sb + OFF_O2FULL + c * 8);
                    TS(1, 12 + c);
                }
            }
            rg.adv(1);
            mbar_wait(sb + OFF_O2FULL + 24, 0);
            TS(wg, 16);
            rg.mma<1>(acc[0], o_base + 3 * CHUNK, false, 2);
            rg.mma<1>(acc[1], o_base + 3 * CHUNK, false, 2);
            ll_write_tile(acc[0], stg, dst, tag, 2 + wg, tw);
            rg.mma<1>(acc[2], o_base + 3 * CHUNK, false, 2);
            ll_write_tile(acc[1], stg + 16384, dst + 1024, tag, 2 + wg, tw);
            wg_wait<0>();
            TS(wg, 17);
            ll_write_tile(acc[2], stg + 32768, dst + 2048, tag, 2 + wg, tw);
        }
        TS(wg, 10);
        {
            const uint4* src = &g_ll[((size_t)(blk * 8 + b) * 56 + wg * 4) * 1024 + hp * 128 + (tid & 127)];
            uint4 pkt[4][8];
#pragma unroll
            for (int t = 0; t < 4; t++)
#pragma unroll
                for (int s = 0; s < 8; s++) {
                    pkt[t][s].y = pkt[t][s].w = (t == 3 && wg == 1) ? tag : ~tag;
                    pkt[t][s].x = pkt[t][s].z = 0;
                }
            if (LL_HINT) {
                const uint4* hp_ = src + (size_t)(lane & 7) * 7168 + (wg == 0 ? 3072 : 2048);
#pragma unroll 1
                for (uint32_t it = 0; it < SPIN_LIMIT; it++) {
                    uint32_t w = tag;
                    if (lane < 8) asm volatile("ld.relaxed.gpu.global.u32 %0, [%1];" : "=r"(w) : "l"(&hp_->w) : "memory");
                    if (__all_sync(0xffffffffu, ((w ^ tag) & 0xffff0000u) == 0)) break;
                    __nanosleep(64);
                }
                TS(wg, 20);
            }
#pragma unroll 1
            for (uint32_t it = 0; it < SPIN_LIMIT; it++) {
#pragma unroll
                for (int t = 0; t < 4; t++)
#pragma unroll
                    for (int s = 0; s < 8; s++)
                        if (((pkt[t][s].y ^ tag) | (pkt[t][s].w ^ tag)) & 0xffff0000u)
                            ld_ll(pkt[t][s], src + (size_t)s * 7168 + t * 1024);
                uint32_t bad = 0;
#pragma unroll
                for (int t = 0; t < 4; t++)
#pragma unroll
                    for (int s = 0; s < 8; s++) bad |= (pkt[t][s].y ^ tag) | (pkt[t][s].w ^ tag);
                if (it == 0) TS(wg, 18);
                if (!(bad & 0xffff0000u)) break;
            }
            __syncwarp();
            TS(wg, 19);
            __nv_bfloat16* orow = prm.out + (size_t)(b * 96 + (hp & 3) * 24 + (lane >> 2)) * 896 + blk * 448 + wg * 256 +
                                  warp * 16 + (hp >> 2) * 8 + (lane & 3) * 2;
#pragma unroll
            for (int t = 0; t < 4; t++)
                if (t < 3 || wg == 0) {
                    float s0 = 0.f, s1 = 0.f, s2 = 0.f, s3 = 0.f, s4 = 0.f, s5 = 0.f;
#pragma unroll
                    for (int s = 0; s < 8; s++) {
                        const uint4 p = pkt[t][s];
                        s0 += __uint_as_float(p.x << 16); s1 += __uint_as_float(p.x & 0xffff0000u);
                        s2 += __uint_as_float(p.z << 16); s3 += __uint_as_float(p.z & 0xffff0000u);
                        s4 += __uint_as_float(p.y << 16); s5 += __uint_as_float(p.w << 16);
                    }
                    uint32_t r0 = pack_bf16(s0, s1), r1 = pack_bf16(s2, s3), r2 = pack_bf16(s4, s5), d0, d1, d2;
                    asm volatile("movmatrix.sync.aligned.m8n8.trans.b16 %0, %1;" : "=r"(d0) : "r"(r0));
                    asm volatile("movmatrix.sync.aligned.m8n8.trans.b16 %0, %1;" : "=r"(d1) : "r"(r1));
                    asm volatile("movmatrix.sync.aligned.m8n8.trans.b16 %0, %1;" : "=r"(d2) : "r"(r2));
                    __nv_bfloat16* o = orow + t * 64;
                    *(uint32_t*)(o) = d0;
                    *(uint32_t*)(o + 8 * 896) = d1;
                    *(uint32_t*)(o + 16 * 896) = d2;
                }
        }
        TS(wg, 11); TSC(wg, 1);
    }
}

typedef CUresult (*EncodeFn)(CUtensorMap*, CUtensorMapDataType, cuuint32_t, void*, const cuuint64_t*, const cuuint64_t*,
                             const cuuint32_t*, const cuuint32_t*, CUtensorMapInterleave, CUtensorMapSwizzle,
                             CUtensorMapL2promotion, CUtensorMapFloatOOBfill);

void encode2d(EncodeFn enc, CUtensorMap* m, const void* p, uint64_t rows, uint64_t cols, uint32_t box_rows,
              CUtensorMapL2promotion promo = CU_TENSOR_MAP_L2_PROMOTION_L2_256B) {
    cuuint64_t dims[2] = {cols, rows};
    cuuint64_t strides[1] = {cols * 2};
    cuuint32_t box[2] = {64, box_rows};
    cuuint32_t es[2] = {1, 1};
    enc(m, CU_TENSOR_MAP_DATA_TYPE_BFLOAT16, 2, const_cast<void*>(p), dims, strides, box, es,
        CU_TENSOR_MAP_INTERLEAVE_NONE, CU_TENSOR_MAP_SWIZZLE_128B, promo,
        CU_TENSOR_MAP_FLOAT_OOB_FILL_NONE);
}

}

extern "C" void kernel_launch(void* const* d_in, const int* in_sizes, int n_in, void* d_out, int out_size) {
    (void)in_sizes; (void)n_in; (void)out_size;
    static EncodeFn enc = nullptr;
    if (!enc) {
        void* fn = nullptr;
        cudaDriverEntryPointQueryResult qr;
        cudaGetDriverEntryPoint("cuTensorMapEncodeTiled", &fn, cudaEnableDefault, &qr);
        enc = (EncodeFn)fn;
        cudaFuncSetAttribute(mha_fused_kernel, cudaFuncAttributeMaxDynamicSharedMemorySize, SMEM_BYTES);
    }
    Params prm;
    for (int blk = 0; blk < 2; blk++) {
        encode2d(enc, &prm.m[blk * 5 + 0], d_in[blk * 5 + 0], 768, 448, 96);
        encode2d(enc, &prm.m[blk * 5 + 1], d_in[blk * 5 + 1], 65536, 256, 64);
        encode2d(enc, &prm.m[blk * 5 + 2], d_in[blk * 5 + 2], 65536, 256, 64, V_PROMO);
        encode2d(enc, &prm.m[blk * 5 + 3], d_in[blk * 5 + 3], 448, 4096, 64);
        encode2d(enc, &prm.m[blk * 5 + 4], d_in[blk * 5 + 4], 4096, 448, 64);
    }
    prm.out = (__nv_bfloat16*)d_out;
    for (int i = 0; i < 10; i++) prm.ptr[i] = (const unsigned char*)d_in[i];
    mha_fused_kernel<<<128, NTHREADS, SMEM_BYTES, cudaStreamPerThread>>>(prm);
}
```

```cpp
#include <cuda_runtime.h>
#include <cuda_bf16.h>
#include <cuda.h>
#include <stdint.h>

namespace {

constexpr int NSTAGE   = 10;
constexpr int BOX      = 8192;
constexpr int CHUNK    = 12288;
constexpr int SLOT     = 49152;
constexpr int OFF_S0   = 0;
constexpr int OFF_S1   = SLOT;
constexpr int OFF_S2   = 2 * SLOT;
constexpr int OFF_RING = 3 * SLOT;
constexpr int OFF_MISC = OFF_RING + NSTAGE * BOX;
constexpr int OFF_FULL   = OFF_MISC;
constexpr int OFF_EMPTY  = OFF_MISC + 256;
constexpr int OFF_XFULL  = OFF_MISC + 384;
constexpr int OFF_O2FULL = OFF_MISC + 440;
constexpr int OFF_O1FREE = OFF_MISC + 472;
constexpr int OFF_EPBAR  = OFF_MISC + 504;
constexpr int OFF_EPOCH  = OFF_MISC + 512;
constexpr int OFF_CMAX   = OFF_MISC + 576;
constexpr int OFF_CSUM   = OFF_CMAX + 768;
constexpr int SMEM_BYTES = 232448;

constexpr int PF_K = 196608;
constexpr int NG1 = 16;
constexpr int NV = 4, NA = 3, NB = NSTAGE - NV - NA;
constexpr int NTHREADS = 384;
constexpr uint32_t SPIN_LIMIT = 1u << 22;

struct __align__(64) Params {
    CUtensorMap m[12];
    __nv_bfloat16* out;
    const unsigned char* ptr[10];
};

__device__ uint4    g_ll[128 * 7 * 8 * 128];
__device__ unsigned g_epoch;
__device__ unsigned g_arrive;

__device__ __forceinline__ uint32_t smem_u32(const void* p) { return (uint32_t)__cvta_generic_to_shared(p); }
__device__ __forceinline__ void mbar_init(uint32_t bar, uint32_t cnt) {
    asm volatile("mbarrier.init.shared::cta.b64 [%0], %1;" :: "r"(bar), "r"(cnt) : "memory");
}
__device__ __forceinline__ void mbar_expect_tx(uint32_t bar, uint32_t bytes) {
    asm volatile("mbarrier.arrive.expect_tx.shared::cta.b64 _, [%0], %1;" :: "r"(bar), "r"(bytes) : "memory");
}
__device__ __forceinline__ void mbar_arrive(uint32_t bar) {
    asm volatile("mbarrier.arrive.shared::cta.b64 _, [%0];" :: "r"(bar) : "memory");
}
__device__ __forceinline__ void mbar_wait(uint32_t bar, uint32_t parity) {
    asm volatile("{\n.reg .pred p;\n.reg .u32 c;\nmov.u32 c, 0;\n"
                 "LW_%=:\nmbarrier.try_wait.parity.shared::cta.b64 p, [%0], %1;\n@p bra LD_%=;\n"
                 "add.u32 c, c, 1;\nsetp.lt.u32 p, c, 4194304;\n@p bra LW_%=;\nLD_%=:\n}"
                 :: "r"(bar), "r"(parity) : "memory");
}
__device__ __forceinline__ void tma2d(uint32_t dst, const CUtensorMap* m, int c0, int c1, uint32_t bar) {
    asm volatile("cp.async.bulk.tensor.2d.shared::cluster.global.mbarrier::complete_tx::bytes [%0], [%1, {%3, %4}], [%2];"
                 :: "r"(dst), "l"(m), "r"(bar), "r"(c0), "r"(c1) : "memory");
}
__device__ __forceinline__ void fence_async() { asm volatile("fence.proxy.async.shared::cta;" ::: "memory"); }
__device__ __forceinline__ void bar_sync(int id, int n) { asm volatile("bar.sync %0, %1;" :: "r"(id), "r"(n) : "memory"); }
__device__ __forceinline__ void wg_fence()  { asm volatile("wgmma.fence.sync.aligned;" ::: "memory"); }
__device__ __forceinline__ void wg_commit() { asm volatile("wgmma.commit_group.sync.aligned;" ::: "memory"); }
template <int N> __device__ __forceinline__ void wg_wait() { asm volatile("wgmma.wait_group.sync.aligned %0;" :: "n"(N) : "memory"); }

__device__ __forceinline__ uint32_t desc_lo(uint32_t addr) { return ((addr & 0x3FFFF) >> 4) | (1u << 16); }

template <int TA>
__device__ __forceinline__ void wgmma96(float (&d)[48], uint32_t da, uint32_t db, int scale_d) {
    asm volatile("{\n.reg .pred p;\n.reg .b64 da, db;\nsetp.ne.b32 p, %50, 0;\n"
        "mov.b64 da, {%48, 0x40000040};\nmov.b64 db, {%49, 0x40000040};\n"
        "wgmma.mma_async.sync.aligned.m64n96k16.f32.bf16.bf16 "
        "{%0,%1,%2,%3,%4,%5,%6,%7,%8,%9,%10,%11,%12,%13,%14,%15,%16,%17,%18,%19,%20,%21,%22,%23,"
        "%24,%25,%26,%27,%28,%29,%30,%31,%32,%33,%34,%35,%36,%37,%38,%39,%40,%41,%42,%43,%44,%45,%46,%47},"
        " da, db, p, 1, 1, %51, 0;\n}"
        : "+f"(d[0]), "+f"(d[1]), "+f"(d[2]), "+f"(d[3]), "+f"(d[4]), "+f"(d[5]), "+f"(d[6]), "+f"(d[7]),
          "+f"(d[8]), "+f"(d[9]), "+f"(d[10]), "+f"(d[11]), "+f"(d[12]), "+f"(d[13]), "+f"(d[14]), "+f"(d[15]),
          "+f"(d[16]), "+f"(d[17]), "+f"(d[18]), "+f"(d[19]), "+f"(d[20]), "+f"(d[21]), "+f"(d[22]), "+f"(d[23]),
          "+f"(d[24]), "+f"(d[25]), "+f"(d[26]), "+f"(d[27]), "+f"(d[28]), "+f"(d[29]), "+f"(d[30]), "+f"(d[31]),
          "+f"(d[32]), "+f"(d[33]), "+f"(d[34]), "+f"(d[35]), "+f"(d[36]), "+f"(d[37]), "+f"(d[38]), "+f"(d[39]),
          "+f"(d[40]), "+f"(d[41]), "+f"(d[42]), "+f"(d[43]), "+f"(d[44]), "+f"(d[45]), "+f"(d[46]), "+f"(d[47])
        : "r"(da), "r"(db), "r"(scale_d), "n"(TA));
}

__device__ __forceinline__ uint32_t pack_bf16(float lo, float hi) {
    uint32_t r;
    asm("cvt.rn.bf16x2.f32 %0, %1, %2;" : "=r"(r) : "f"(hi), "f"(lo));
    return r;
}
__device__ __forceinline__ void stsm_x4_t(uint32_t addr, uint32_t r0, uint32_t r1, uint32_t r2, uint32_t r3) {
    asm volatile("stmatrix.sync.aligned.m8n8.x4.trans.shared.b16 [%0], {%1,%2,%3,%4};"
                 :: "r"(addr), "r"(r0), "r"(r1), "r"(r2), "r"(r3) : "memory");
}
__device__ __forceinline__ float ex2(float x) { float y; asm("ex2.approx.ftz.f32 %0, %1;" : "=f"(y) : "f"(x)); return y; }
__device__ __forceinline__ float4 lds128(uint32_t addr) {
    float4 v;
    asm volatile("ld.shared.v4.f32 {%0,%1,%2,%3}, [%4];" : "=f"(v.x), "=f"(v.y), "=f"(v.z), "=f"(v.w) : "r"(addr) : "memory");
    return v;
}
__device__ __forceinline__ void ld_ll(uint4& p, const uint4* a) {
    asm volatile("{\n.reg .b64 lo, hi;\nld.relaxed.gpu.global.v2.b64 {lo, hi}, [%4];\n"
                 "mov.b64 {%0,%1}, lo;\nmov.b64 {%2,%3}, hi;\n}"
                 : "=r"(p.x), "=r"(p.y), "=r"(p.z), "=r"(p.w) : "l"(a) : "memory");
}
__device__ __forceinline__ uint32_t touch_line(const void* a) {
    uint32_t v;
    asm volatile("ld.global.cg.L2::128B.u32 %0, [%1];" : "=r"(v) : "l"(a));
    return v;
}
__device__ __forceinline__ int f2ord(float f) { int i = __float_as_int(f); return i ^ ((i >> 31) & 0x7fffffff); }
__device__ __forceinline__ float ord2f(int i) { return __int_as_float(i ^ ((i >> 31) & 0x7fffffff)); }

struct Ring {
    static constexpr uint32_t base = 1024;
    uint32_t fullb;
    uint32_t par;
    uint32_t pend;
    bool     leader;
    template <int TA, int STEP, int LO, int HI>
    __device__ __forceinline__ void mma(float (&acc)[48], uint32_t& cur, uint32_t b_addr, bool zero_first) {
        mbar_wait(fullb + cur * 8, (par >> cur) & 1);
        par ^= 1u << cur;
        const uint32_t da = desc_lo(base + OFF_RING + (HI > NSTAGE && cur >= NSTAGE ? cur - NG1 : cur) * BOX), db = desc_lo(b_addr);
        wg_fence();
#pragma unroll
        for (int ks = 0; ks < 4; ks++)
            wgmma96<TA>(acc, da + (TA ? ks * 128 : ks * 2), db + ks * 2, (ks > 0 || !zero_first) ? 1 : 0);
        wg_commit();
        wg_wait<1>();
        if (pend) mbar_arrive(pend);
        pend = leader ? base + OFF_EMPTY + cur * 8 : 0;
        cur += STEP;
        if (cur >= HI) cur -= HI - LO;
    }
    __device__ __forceinline__ void drain() {
        wg_wait<0>();
        if (pend) mbar_arrive(pend);
        pend = 0;
    }
};

__device__ __forceinline__ uint32_t late_tid() { uint32_t t; asm volatile("mov.u32 %0, %%tid.x;" : "=r"(t)); return t; }
__device__ __forceinline__ uint32_t late_bid() { uint32_t t; asm volatile("mov.u32 %0, %%ctaid.x;" : "=r"(t)); return t; }
__device__ __forceinline__ uint32_t st_lane() {
    const uint32_t t = late_tid();
    return 1024 + (((t >> 4) & 1) * 8 + (t & 7)) * 128 + (((((t >> 5) & 3) * 2 + ((t >> 3) & 1)) ^ (t & 7)) << 4);
}

__device__ __forceinline__ void store_tile(const float (&a)[48], uint32_t addr) {
#pragma unroll
    for (int jj = 0; jj < 6; jj++)
        stsm_x4_t(addr + jj * 2048,
                  pack_bf16(a[8 * jj + 0], a[8 * jj + 1]), pack_bf16(a[8 * jj + 2], a[8 * jj + 3]),
                  pack_bf16(a[8 * jj + 4], a[8 * jj + 5]), pack_bf16(a[8 * jj + 6], a[8 * jj + 7]));
}
__device__ __forceinline__ void store_tile_scaled(const float (&a)[48], uint32_t addr, uint32_t inv_addr) {
#pragma unroll
    for (int jj = 0; jj < 6; jj++) {
        const float4 s = lds128(inv_addr + jj * 16);
        stsm_x4_t(addr + jj * 2048,
                  pack_bf16(a[8 * jj + 0] * s.x, a[8 * jj + 1] * s.y), pack_bf16(a[8 * jj + 2] * s.x, a[8 * jj + 3] * s.y),
                  pack_bf16(a[8 * jj + 4] * s.z, a[8 * jj + 5] * s.w), pack_bf16(a[8 * jj + 6] * s.z, a[8 * jj + 7] * s.w));
    }
}

__device__ __forceinline__ void ll_write_tile(const float (&a)[48], uint4* dst, uint32_t tag, uint32_t own, uint32_t own_addr) {
#pragma unroll
    for (int pk = 0; pk < 8; pk++) {
        const int r = 12 * (pk & 3) + 2 * (pk >> 2);
        const uint32_t x = pack_bf16(a[r], a[r + 1]);
        const uint32_t z = pack_bf16(a[r + 4], a[r + 5]);
        const uint32_t yw = pack_bf16(a[r + 8], a[r + 9]);
        const uint32_t y = (yw & 0xffffu) | tag, w = (yw >> 16) | tag;
        if (pk != own)
            asm volatile("{\n.reg .b64 lo, hi;\nmov.b64 lo, {%1,%2};\nmov.b64 hi, {%3,%4};\n"
                         "st.relaxed.gpu.global.v2.b64 [%0], {lo, hi};\n}"
                         :: "l"(dst + pk * 128), "r"(x), "r"(y), "r"(z), "r"(w) : "memory");
        else
            asm volatile("st.shared.v4.b32 [%0], {%1,%2,%3,%4};" :: "r"(own_addr), "r"(x), "r"(y), "r"(z), "r"(w) : "memory");
    }
}
__device__ __forceinline__ uint32_t ll_tag(uint32_t sb) {
    uint32_t tag;
    mbar_wait(sb + OFF_EPBAR, 0);
    asm volatile("ld.shared.u32 %0, [%1];" : "=r"(tag) : "r"(sb + OFF_EPOCH) : "memory");
    return tag;
}
__device__ __forceinline__ uint4* ll_dst() {
    const uint32_t bid = late_bid(), tid = late_tid();
    const uint32_t cta = ((bid >> 6) * 8 + ((bid >> 4) & 3) * 2 + (bid & 1)) * 8 + ((bid >> 1) & 7);
    return &g_ll[(cta * 7 + (tid >> 7) * 4) * 1024 + (tid & 127)];
}

template <bool FIRST>
__device__ __forceinline__ void tile_max(float (&mx)[24], const float (&a)[48]) {
#pragma unroll
    for (int i = 0; i < 24; i++) {
        const int r = 4 * (i >> 1) + (i & 1);
        const float m = fmaxf(a[r], a[r + 2]);
        mx[i] = FIRST ? m : fmaxf(mx[i], m);
    }
}
__device__ __forceinline__ void softmax_max(const float (&mx)[24], uint32_t cmax, int lane) {
    const bool b4 = lane & 16, b3 = lane & 8, b2 = lane & 4;
    float m12[12], m6[6];
#pragma unroll
    for (int i = 0; i < 12; i++) {
        const float snd = b4 ? mx[i] : mx[i + 12], keep = b4 ? mx[i + 12] : mx[i];
        m12[i] = fmaxf(keep, __shfl_xor_sync(0xffffffffu, snd, 16));
    }
#pragma unroll
    for (int i = 0; i < 6; i++) {
        const float snd = b3 ? m12[i] : m12[i + 6], keep = b3 ? m12[i + 6] : m12[i];
        m6[i] = fmaxf(keep, __shfl_xor_sync(0xffffffffu, snd, 8));
    }
#pragma unroll
    for (int i = 0; i < 3; i++) {
        const float snd = b2 ? m6[i] : m6[i + 3], keep = b2 ? m6[i + 3] : m6[i];
        const float m = fmaxf(keep, __shfl_xor_sync(0xffffffffu, snd, 4));
        asm volatile("red.shared.max.s32 [%0], %1;"
                     :: "r"(cmax + ((b4 ? 12 : 0) + (b3 ? 6 : 0) + (b2 ? 3 : 0) + i) * 4), "r"(f2ord(m)) : "memory");
    }
}
__device__ __forceinline__ void softmax_exp(float (&a0)[48], float (&a1)[48], uint32_t cmax, int lane) {
    const float C = 0.0625f * 1.4426950408889634f;
    const uint32_t csum = cmax + (OFF_CSUM - OFF_CMAX);
    const bool b4 = lane & 16, b3 = lane & 8, b2 = lane & 4;
#pragma unroll
    for (int h = 0; h < 2; h++) {
        float v[12], t6[6];
#pragma unroll
        for (int j3 = 0; j3 < 3; j3++) {
            const int jj = 3 * h + j3;
            const float4 mo = lds128(cmax + jj * 16);
            const float m0 = ord2f(__float_as_int(mo.x)) * C, m1 = ord2f(__float_as_int(mo.y)) * C;
            const float m2 = ord2f(__float_as_int(mo.z)) * C, m3 = ord2f(__float_as_int(mo.w)) * C;
            float s0 = 0.f, s1 = 0.f, s2 = 0.f, s3 = 0.f;
#pragma unroll
            for (int t = 0; t < 2; t++) {
                float* a = t == 0 ? &a0[8 * jj] : &a1[8 * jj];
                const float p0 = ex2(fmaf(a[0], C, -m0)), p1 = ex2(fmaf(a[1], C, -m1));
                const float p2 = ex2(fmaf(a[2], C, -m0)), p3 = ex2(fmaf(a[3], C, -m1));
                const float p4 = ex2(fmaf(a[4], C, -m2)), p5 = ex2(fmaf(a[5], C, -m3));
                const float p6 = ex2(fmaf(a[6], C, -m2)), p7 = ex2(fmaf(a[7], C, -m3));
                s0 += p0 + p2; s1 += p1 + p3; s2 += p4 + p6; s3 += p5 + p7;
                a[0] = p0; a[1] = p1; a[2] = p2; a[3] = p3; a[4] = p4; a[5] = p5; a[6] = p6; a[7] = p7;
            }
            v[4 * j3 + 0] = s0; v[4 * j3 + 1] = s1; v[4 * j3 + 2] = s2; v[4 * j3 + 3] = s3;
        }
#pragma unroll
        for (int i = 0; i < 6; i++) {
            const float snd = b4 ? v[i] : v[i + 6], keep = b4 ? v[i + 6] : v[i];
            t6[i] = keep + __shfl_xor_sync(0xffffffffu, snd, 16);
        }
#pragma unroll
        for (int i = 0; i < 3; i++) {
            const float snd = b3 ? t6[i] : t6[i + 3], keep = b3 ? t6[i + 3] : t6[i];
            float o = keep + __shfl_xor_sync(0xffffffffu, snd, 8);
            o += __shfl_xor_sync(0xffffffffu, o, 4);
            if (!b2)
                asm volatile("red.shared.add.u32 [%0], %1;"
                             :: "r"(csum + (12 * h + (b4 ? 6 : 0) + (b3 ? 3 : 0) + i) * 4), "r"(__float2uint_rn(o * 4194304.f)) : "memory");
        }
    }
}
__device__ __forceinline__ void invert_sum(uint32_t addr) {
    uint32_t sum;
    asm volatile("ld.shared.u32 %0, [%1];" : "=r"(sum) : "r"(addr) : "memory");
    const float inv = __fdividef(4194304.f, (float)sum);
    asm volatile("st.shared.f32 [%0], %1;" :: "r"(addr), "f"(inv) : "memory");
}

__global__ void __launch_bounds__(NTHREADS, 1)
mha_fused_kernel(const __grid_constant__ Params prm) {
    extern __shared__ __align__(1024) unsigned char smem_raw[];
    constexpr uint32_t sb = 1024;
    if ((smem_u32(smem_raw) & 0xffffffu) != sb) return;
    const int tid = threadIdx.x, wg = tid >> 7, lane = tid & 31, warp = (tid >> 5) & 3;
    const int bid = blockIdx.x;
    const int blk = bid >> 6, b = ((bid >> 4) & 3) * 2 + (bid & 1), hp = (bid >> 1) & 7;

    const CUtensorMap* mbase = &prm.m[blk * 6];
    if (tid < 128) {
        if (tid == 0) {
#pragma unroll
            for (int i = 0; i < NG1; i++) mbar_init(sb + OFF_FULL + i * 8, 1);
        } else if (tid == 32) {
#pragma unroll
            for (int i = 0; i < NG1; i++) mbar_init(sb + OFF_FULL + 128 + i * 8, 1);
        } else if (tid == 64) {
#pragma unroll
            for (int i = 0; i < NG1; i++) mbar_init(sb + OFF_EMPTY + i * 8, 4);
            mbar_init(sb + OFF_EPBAR, 1);
        } else if (tid == 96) {
#pragma unroll
            for (int i = 0; i < 7; i++) mbar_init(sb + OFF_XFULL + i * 8, 1);
#pragma unroll
            for (int i = 0; i < 4; i++) { mbar_init(sb + OFF_O2FULL + i * 8, 128); mbar_init(sb + OFF_O1FREE + i * 8, 4); }
        }
        asm volatile("fence.mbarrier_init.release.cluster;" ::: "memory");
    } else if (tid < 320) {
        asm volatile("st.shared.u32 [%0], %1;" :: "r"(sb + OFF_CMAX + (tid - 128) * 4), "r"(0x80000000u) : "memory");
        asm volatile("st.shared.u32 [%0], %1;" :: "r"(sb + OFF_CSUM + (tid - 128) * 4), "r"(0u) : "memory");
    }
    __syncthreads();

    if (wg == 2) {
        asm volatile("setmaxnreg.dec.sync.aligned.u32 24;");
        const int h0 = 2 * hp, kv0 = (b * 16 + h0) * 512;
        if (warp >= 2) {
            const int pt = tid - 320;
            uint32_t sink = 0;
            {
                const unsigned char* qp = prm.ptr[blk * 5 + 3] + (size_t)(b * 8 + (pt >> 3)) * 8192 + hp * 1024 + (pt & 7) * 128;
#pragma unroll
                for (int kc = 0; kc < 7; kc++) sink += touch_line(qp + kc * 524288);
            }
            const unsigned char* kp = prm.ptr[blk * 5 + 1] + (size_t)kv0 * 512 + pt * 128;
            __nanosleep(1500);
#pragma unroll 1
            for (int i = 0; i < PF_K / 32768; i++) {
                const uint32_t a0 = touch_line(kp + i * 32768), a1 = touch_line(kp + i * 32768 + 8192);
                const uint32_t a2 = touch_line(kp + i * 32768 + 16384), a3 = touch_line(kp + i * 32768 + 24576);
                sink += a0 + a1 + a2 + a3;
            }
            if (sink == 0x9e3779b9u) asm volatile("st.shared.u32 [%0], %1;" :: "r"(sb + OFF_EPOCH + 4), "r"(sink) : "memory");
            if (tid == 352) {
                unsigned epoch;
                asm volatile("ld.relaxed.gpu.global.u32 %0, [%1];" : "=r"(epoch) : "l"(&g_epoch) : "memory");
                asm volatile("st.shared.u32 [%0], %1;" :: "r"(sb + OFF_EPOCH), "r"((epoch % 65535u + 1u) << 16) : "memory");
                mbar_arrive(sb + OFF_EPBAR);
                const unsigned old = atomicAdd(&g_arrive, 1u + (epoch & 0u));
                if (old == gridDim.x - 1) { g_arrive = 0; g_epoch = epoch + 1; }
            }
        } else if (warp == 1 && lane < 7) {
            mbar_expect_tx(sb + OFF_XFULL + lane * 8, CHUNK);
            tma2d(sb + OFF_S0 + lane * CHUNK, mbase, lane * 64, b * 96, sb + OFF_XFULL + lane * 8);
        }
        if (warp < 3) {
#pragma unroll 1
            for (int batch = warp < 2 ? 0 : 3; batch < (warp == 0 ? 5 : 4); batch++) {
                int owner, mi, c0, c1, use, slot, cnt;
                if (batch < 3) {
                    const int n = batch * 64 + 2 * lane + warp;
                    owner = warp;
                    if (n < 56) {
                        mi = 3; c0 = (h0 + 1 - owner) * 256 + ((n >> 1) & 3) * 64; c1 = (n >> 3) * 64;
                    } else if (n < 120) {
                        const int m = n - 56;
                        mi = 1; c0 = ((m >> 1) & 3) * 64; c1 = kv0 + ((m >> 3) * 2 + owner) * 64;
                    } else {
                        const int m = n - 120;
                        mi = 2; c0 = (owner * 2 + ((m >> 1) & 1)) * 64; c1 = kv0 + (m >> 2) * 64;
                    }
                    if (n < 56) { use = n >> 4; slot = n & 15; }
                    else { use = (n - 56) / NSTAGE; slot = n - 56 - use * NSTAGE; use += slot < 8 ? 4 : 3; }
                    cnt = batch < 2 ? 32 : 12;
                } else if (batch == 4) {
                    owner = 0; mi = 4; c0 = 192; c1 = h0 * 256 + 448;
                    slot = 32 % NV; use = 32 / NV + (slot < 6 ? 14 : slot < 8 ? 13 : 12);
                    cnt = 1;
                } else {
                    bar_sync(3, 96);
                    owner = warp != 1;
                    if (warp == 0) {
                        mi = 5; c0 = (lane >> 3) * 64; c1 = kv0 + 512 + (lane & 7) * 64;
                        use = lane / NV; slot = lane - use * NV;
                    } else {
                        const int g = warp == 1 ? lane >> 2 : lane / 3, i = warp == 1 ? lane & 3 : 4 + lane - 3 * g;
                        mi = 4; c0 = i * 64; c1 = h0 * 256 + ((0x76534210u >> (4 * (g & 7))) & 7) * 64;
                        if (warp == 1) { use = lane / NA; slot = NV + lane - use * NA; }
                        else           { use = lane / NB; slot = NV + NA + lane - use * NB; }
                    }
                    use += slot < 6 ? 14 : slot < 8 ? 13 : 12;
                    cnt = warp == 0 ? 32 : warp == 1 ? 31 : 24;
                }
                const uint32_t eb = sb + OFF_EMPTY + slot * 8, fb = sb + OFF_FULL + owner * 128 + slot * 8;
                const uint32_t dst = sb + OFF_RING + (slot < NSTAGE ? slot : slot - NG1) * BOX;
                const CUtensorMap* mp = mbase + mi;
#pragma unroll 1
                for (int i = 0; i < cnt; i++) {
                    if (lane == i) {
                        mbar_wait(eb, (use ^ 1) & 1);
                        mbar_expect_tx(fb, BOX);
                        tma2d(dst, mp, c0, c1, fb);
                    }
                    __syncwarp();
                }
            }
        }
    } else {
        asm volatile("setmaxnreg.inc.sync.aligned.u32 240;");
        float acc[4][48];
        Ring rg;
        rg.fullb = sb + OFF_FULL + wg * 128; rg.par = 0; rg.pend = 0; rg.leader = (lane == 0);
        uint32_t cur = wg;
#pragma unroll 1
        for (int kc = 0; kc < 7; kc++) {
            mbar_wait(sb + OFF_XFULL + kc * 8, 0);
#pragma unroll
            for (int mt = 0; mt < 4; mt++) rg.mma<1, 2, 0, NG1>(acc[mt], cur, sb + OFF_S0 + kc * CHUNK, kc == 0);
        }
        rg.drain();
        cur = wg;
        bar_sync(1, 256);
        {
            const uint32_t qa = st_lane() + (wg == 1 ? OFF_S2 : OFF_S0);
#pragma unroll
            for (int mt = 0; mt < 4; mt++) store_tile(acc[mt], qa + mt * CHUNK);
        }
        fence_async();
        bar_sync(1, 256);
        const uint32_t o_base = sb + OFF_S2;
        const uint32_t cinv = sb + OFF_CSUM + (lane & 3) * 96;
#pragma unroll 1
        for (int kc = 0; kc < 4; kc++) rg.mma<0, 2, 0, NSTAGE>(acc[0], cur, sb + OFF_S2 + kc * CHUNK, kc == 0);
#pragma unroll 1
        for (int item = 0; item < 2; item++) {
            const uint32_t q_base = sb + (item == 0 ? OFF_S2 : OFF_S0);
            float mx[24];
#pragma unroll
            for (int t = 1; t < 4; t++) {
#pragma unroll 1
                for (int kc = 0; kc < 4; kc++) rg.mma<0, 2, 0, NSTAGE>(acc[t], cur, q_base + kc * CHUNK, kc == 0);
                if (t == 1) tile_max<true>(mx, acc[0]);
                if (t > 1) tile_max<false>(mx, acc[t - 1]);
            }
            rg.drain();
            tile_max<false>(mx, acc[3]);
            const uint32_t cmax = sb + OFF_CMAX + item * 384 + (lane & 3) * 96;
            const uint32_t p_off = (item == 0 ? OFF_S1 : OFF_S0) + wg * CHUNK;
            softmax_max(mx, cmax, lane);
            bar_sync(1, 256);
            softmax_exp(acc[0], acc[1], cmax, lane);
            store_tile(acc[0], st_lane() + p_off);
            store_tile(acc[1], st_lane() + p_off + 2 * CHUNK);
            if (item == 0) {
#pragma unroll 1
                for (int kc = 0; kc < 4; kc++) rg.mma<0, 2, 0, NSTAGE>(acc[0], cur, sb + OFF_S0 + kc * CHUNK, kc == 0);
            } else {
#pragma unroll 1
                for (int kc = 0; kc < 2; kc++) {
                    rg.mma<1, 2, 0, NSTAGE>(acc[0], cur, sb + OFF_S1 + kc * CHUNK, kc == 0);
                    rg.mma<1, 2, 0, NSTAGE>(acc[1], cur, sb + OFF_S1 + kc * CHUNK, kc == 0);
                }
            }
            rg.drain();
            softmax_exp(acc[2], acc[3], cmax, lane);
            if (item == 1) {
                if (tid < 96) invert_sum(sb + OFF_CSUM + tid * 4);
#pragma unroll 1
                for (int kc = 2; kc < 8; kc++) {
                    rg.mma<1, 2, 0, NSTAGE>(acc[0], cur, sb + OFF_S1 + kc * CHUNK, false);
                    rg.mma<1, 2, 0, NSTAGE>(acc[1], cur, sb + OFF_S1 + kc * CHUNK, false);
                }
                rg.drain();
                bar_sync(1, 256);
                const uint32_t oa = st_lane() + OFF_S2 + 2 * wg * CHUNK;
                store_tile_scaled(acc[0], oa, cinv);
                store_tile_scaled(acc[1], oa + CHUNK, cinv);
            }
            const uint32_t p_addr = st_lane() + p_off;
            store_tile(acc[2], p_addr + 4 * CHUNK);
            store_tile(acc[3], p_addr + 6 * CHUNK);
            fence_async();
        }
        bar_sync(1, 256);
        if (wg == 0) {
            cur = NV;
#pragma unroll 1
            for (int hs = 0; hs < 7; hs++) {
                const int part = (0x68 >> hs) & 1, ch = (0x2130210 >> (4 * hs)) & 3;
                const uint32_t oc = o_base + ch * CHUNK;
                if (part) mbar_wait(sb + OFF_O2FULL + ch * 8, 0);
#pragma unroll
                for (int i = 0; i < 4; i++) rg.mma<1, 1, NV, NV + NA>(acc[i], cur, oc, hs == 0);
                rg.drain();
                if (!part && lane == 0) mbar_arrive(sb + OFF_O1FREE + ch * 8);
            }
            const uint32_t tag = ll_tag(sb);
            uint4* const dst = ll_dst();
            const uint32_t own = (late_bid() >> 1) & 7, oa = sb + OFF_S0 + late_tid() * 16;
            mbar_wait(sb + OFF_O2FULL + 24, 0);
            rg.mma<1, 1, NV, NV + NA>(acc[0], cur, o_base + 3 * CHUNK, false);
            rg.mma<1, 1, NV, NV + NA>(acc[1], cur, o_base + 3 * CHUNK, false);
            ll_write_tile(acc[0], dst, tag, own, oa);
            rg.mma<1, 1, NV, NV + NA>(acc[2], cur, o_base + 3 * CHUNK, false);
            ll_write_tile(acc[1], dst + 1024, tag, own, oa + 4096);
            cur = 32 % NV;
            rg.mma<1, 1, NV, NV + NA>(acc[3], cur, o_base + 3 * CHUNK, false);
            ll_write_tile(acc[2], dst + 2048, tag, own, oa + 8192);
            wg_wait<0>();
            ll_write_tile(acc[3], dst + 3072, tag, own, oa + 12288);
        } else {
            uint32_t curw = NV + NA;
            cur = 0;
            if (tid < 128 + 96) invert_sum(sb + OFF_CSUM + 384 + (tid - 128) * 4);
            bar_sync(2, 128);
#pragma unroll 1
            for (int hs = 0; hs < 8; hs++) {
                const int part = (0x68 >> hs) & 1, ch = (0x2130210 >> (4 * hs)) & 3;
                const uint32_t oc = o_base + ch * CHUNK;
                const uint32_t pc = sb + OFF_S0 + (hs & 1) * 4 * CHUNK;
#pragma unroll
                for (int i = 0; i < 4; i++) {
                    rg.mma<1, 1, 0, NV>(acc[3], cur, pc + i * CHUNK, (hs & 1) == 0 && i == 0);
                    if (hs < 7 && i < 3) {
                        if (i == 0 && part) mbar_wait(sb + OFF_O2FULL + ch * 8, 0);
                        rg.mma<1, 1, NV + NA, NSTAGE>(acc[i], curw, oc, hs == 0);
                    }
                }
                if (hs & 1) {
                    const int c = hs >> 1;
                    rg.drain();
                    mbar_wait(sb + OFF_O1FREE + c * 8, 0);
                    store_tile_scaled(acc[3], st_lane() + OFF_S2 + c * CHUNK, cinv + 384);
                    fence_async();
                    mbar_arrive(sb + OFF_O2FULL + c * 8);
                }
            }
            const uint32_t tag = ll_tag(sb);
            uint4* const dst = ll_dst();
            const uint32_t own = (late_bid() >> 1) & 7, oa = sb + OFF_S0 + late_tid() * 16;
            mbar_wait(sb + OFF_O2FULL + 24, 0);
            rg.mma<1, 1, NV + NA, NSTAGE>(acc[0], curw, o_base + 3 * CHUNK, false);
            rg.mma<1, 1, NV + NA, NSTAGE>(acc[1], curw, o_base + 3 * CHUNK, false);
            ll_write_tile(acc[0], dst, tag, own, oa);
            rg.mma<1, 1, NV + NA, NSTAGE>(acc[2], curw, o_base + 3 * CHUNK, false);
            ll_write_tile(acc[1], dst + 1024, tag, own, oa + 4096);
            wg_wait<0>();
            ll_write_tile(acc[2], dst + 2048, tag, own, oa + 8192);
        }
        {
            const uint32_t tag = ll_tag(sb);
            const int bid2 = late_bid(), tid2 = late_tid();
            const int blk = bid2 >> 6, b = ((bid2 >> 4) & 3) * 2 + (bid2 & 1), hp = (bid2 >> 1) & 7;
            const int wg = tid2 >> 7, lane = tid2 & 31, warp = (tid2 >> 5) & 3;
            const uint4* src = &g_ll[((blk * 8 + b) * 56 + wg * 4) * 1024 + hp * 128 + (tid2 & 127)];
            uint4 pkt[4][8];
#pragma unroll
            for (int t = 0; t < 4; t++)
#pragma unroll
                for (int s = 0; s < 8; s++) {
                    pkt[t][s].y = pkt[t][s].w = (t == 3 && wg == 1) ? tag : ~tag;
                    pkt[t][s].x = pkt[t][s].z = 0;
                }
            {
                const uint4* hp_ = src + (size_t)(lane & 7) * 7168 + (wg == 0 ? 3072 : 2048);
                uint32_t todo = 0xffu & ~(1u << hp);
#pragma unroll
                for (int s = 0; s < 8; s++)
                    if (s == hp) {
#pragma unroll
                        for (int t = 0; t < 4; t++)
                            if (t < 3 || wg == 0)
                                asm volatile("ld.shared.v4.b32 {%0,%1,%2,%3}, [%4];"
                                             : "=r"(pkt[t][s].x), "=r"(pkt[t][s].y), "=r"(pkt[t][s].z), "=r"(pkt[t][s].w)
                                             : "r"(sb + OFF_S0 + tid2 * 16 + t * 4096) : "memory");
                    }
#pragma unroll 1
                for (uint32_t it = 0; it < SPIN_LIMIT && todo; it++) {
                    uint32_t w = ~tag;
                    if (lane < 8 && ((todo >> lane) & 1))
                        asm volatile("ld.relaxed.gpu.global.u32 %0, [%1];" : "=r"(w) : "l"(&hp_->w) : "memory");
                    const uint32_t rdy = __ballot_sync(0xffffffffu, ((w ^ tag) & 0xffff0000u) == 0);
#pragma unroll
                    for (int s = 0; s < 8; s++)
                        if ((rdy >> s) & 1) {
#pragma unroll
                            for (int t = 0; t < 4; t++)
                                if (t < 3 || wg == 0) ld_ll(pkt[t][s], src + (size_t)s * 7168 + t * 1024);
                        }
                    todo &= ~rdy;
                    if (!rdy) __nanosleep(64);
                }
            }
#pragma unroll 1
            for (uint32_t it = 0; it < SPIN_LIMIT; it++) {
                uint32_t bad = 0;
#pragma unroll
                for (int t = 0; t < 4; t++)
#pragma unroll
                    for (int s = 0; s < 8; s++) bad |= (pkt[t][s].y ^ tag) | (pkt[t][s].w ^ tag);
                if (!(bad & 0xffff0000u)) break;
#pragma unroll
                for (int t = 0; t < 4; t++)
#pragma unroll
                    for (int s = 0; s < 8; s++)
                        if (((pkt[t][s].y ^ tag) | (pkt[t][s].w ^ tag)) & 0xffff0000u)
                            ld_ll(pkt[t][s], src + (size_t)s * 7168 + t * 1024);
            }
            __syncwarp();
            __nv_bfloat16* orow = prm.out + (size_t)(b * 96 + (hp & 3) * 24 + (lane >> 2)) * 896 + blk * 448 + wg * 256 +
                                  warp * 16 + (hp >> 2) * 8 + (lane & 3) * 2;
#pragma unroll
            for (int t = 0; t < 4; t++)
                if (t < 3 || wg == 0) {
                    float s0 = 0.f, s1 = 0.f, s2 = 0.f, s3 = 0.f, s4 = 0.f, s5 = 0.f;
#pragma unroll
                    for (int s = 0; s < 8; s++) {
                        const uint4 p = pkt[t][s];
                        s0 += __uint_as_float(p.x << 16); s1 += __uint_as_float(p.x & 0xffff0000u);
                        s2 += __uint_as_float(p.z << 16); s3 += __uint_as_float(p.z & 0xffff0000u);
                        s4 += __uint_as_float(p.y << 16); s5 += __uint_as_float(p.w << 16);
                    }
                    uint32_t r0 = pack_bf16(s0, s1), r1 = pack_bf16(s2, s3), r2 = pack_bf16(s4, s5), d0, d1, d2;
                    asm volatile("movmatrix.sync.aligned.m8n8.trans.b16 %0, %1;" : "=r"(d0) : "r"(r0));
                    asm volatile("movmatrix.sync.aligned.m8n8.trans.b16 %0, %1;" : "=r"(d1) : "r"(r1));
                    asm volatile("movmatrix.sync.aligned.m8n8.trans.b16 %0, %1;" : "=r"(d2) : "r"(r2));
                    __nv_bfloat16* o = orow + t * 64;
                    *(uint32_t*)(o) = d0;
                    *(uint32_t*)(o + 8 * 896) = d1;
                    *(uint32_t*)(o + 16 * 896) = d2;
                }
        }
    }
}

typedef CUresult (*EncodeFn)(CUtensorMap*, CUtensorMapDataType, cuuint32_t, void*, const cuuint64_t*, const cuuint64_t*,
                             const cuuint32_t*, const cuuint32_t*, CUtensorMapInterleave, CUtensorMapSwizzle,
                             CUtensorMapL2promotion, CUtensorMapFloatOOBfill);

void encode2d(EncodeFn enc, CUtensorMap* m, const void* p, uint64_t rows, uint64_t cols, uint32_t box_rows,
              CUtensorMapL2promotion promo = CU_TENSOR_MAP_L2_PROMOTION_L2_256B) {
    cuuint64_t dims[2] = {cols, rows};
    cuuint64_t strides[1] = {cols * 2};
    cuuint32_t box[2] = {64, box_rows};
    cuuint32_t es[2] = {1, 1};
    enc(m, CU_TENSOR_MAP_DATA_TYPE_BFLOAT16, 2, const_cast<void*>(p), dims, strides, box, es,
        CU_TENSOR_MAP_INTERLEAVE_NONE, CU_TENSOR_MAP_SWIZZLE_128B, promo,
        CU_TENSOR_MAP_FLOAT_OOB_FILL_NONE);
}

}

extern "C" void kernel_launch(void* const* d_in, const int* in_sizes, int n_in, void* d_out, int out_size) {
    (void)in_sizes; (void)n_in; (void)out_size;
    static EncodeFn enc = nullptr;
    if (!enc) {
        void* fn = nullptr;
        cudaDriverEntryPointQueryResult qr;
        cudaGetDriverEntryPoint("cuTensorMapEncodeTiled", &fn, cudaEnableDefault, &qr);
        enc = (EncodeFn)fn;
        cudaFuncSetAttribute(mha_fused_kernel, cudaFuncAttributeMaxDynamicSharedMemorySize, SMEM_BYTES);
    }
    Params prm;
    for (int blk = 0; blk < 2; blk++) {
        encode2d(enc, &prm.m[blk * 6 + 0], d_in[blk * 5 + 0], 768, 448, 96);
        encode2d(enc, &prm.m[blk * 6 + 1], d_in[blk * 5 + 1], 65536, 256, 64);
        encode2d(enc, &prm.m[blk * 6 + 2], d_in[blk * 5 + 2], 65536, 256, 64);
        encode2d(enc, &prm.m[blk * 6 + 5], d_in[blk * 5 + 2], 65536, 256, 64, CU_TENSOR_MAP_L2_PROMOTION_L2_128B);
        encode2d(enc, &prm.m[blk * 6 + 3], d_in[blk * 5 + 3], 448, 4096, 64);
        encode2d(enc, &prm.m[blk * 6 + 4], d_in[blk * 5 + 4], 4096, 448, 64);
    }
    prm.out = (__nv_bfloat16*)d_out;
    for (int i = 0; i < 10; i++) prm.ptr[i] = (const unsigned char*)d_in[i];
    mha_fused_kernel<<<128, NTHREADS, SMEM_BYTES, cudaStreamPerThread>>>(prm);
}
```
